```python
import torch

def _softmax(x, axis=-1):
    return torch.softmax(x, dim=axis)
def _gelu(x):
    return torch.nn.functional.gelu(x, approximate="tanh")
def _silu(x):
    return torch.nn.functional.silu(x)
def _sigmoid(x):
    return torch.sigmoid(x)
def _layernorm(x, axis=-1, eps=1e-5):
    m = x.mean(dim=axis, keepdim=True)
    v = x.var(dim=axis, keepdim=True, unbiased=False)
    return (x - m) / torch.sqrt(v + eps)
def _scatter_add(tgt, idx, src, axis=0):
    return tgt.clone().index_add_(axis, idx, src)
def _segment_sum(src, seg, n):
    out = torch.zeros((n,) + src.shape[1:], dtype=src.dtype)
    return out.index_add_(0, seg, src)
def _pad(x, pw):
    flat = tuple(v for pair in reversed(pw) for v in pair)
    return torch.nn.functional.pad(x, flat)

kernel_name = 'sequential_preLN__softmax_full_mha__dense_activation_silu__prompt'

def setup_inputs():

    _w = (lambda a: (lambda t: t.to(torch.bfloat16) if t.is_floating_point() else t)(torch.as_tensor(a)))
    def _A_setup():
        B, S, D = 1, 2048, 448
        return {
            "x": _w((lambda *s: torch.randn(*s, dtype=torch.bfloat16) * 0.05)(B, S, D)),
            "wqkv": _w((lambda *s: torch.randn(*s, dtype=torch.bfloat16) * 0.05)(D, 3 * D)),
            "wo": _w((lambda *s: torch.randn(*s, dtype=torch.bfloat16) * 0.05)(D, D)),
        }
    _A_in = _A_setup()

    def _B_setup():
        B, S, D, F = 1, 2048, 448, 1792
        return {
            "x": _w((lambda *s: torch.randn(*s, dtype=torch.bfloat16) * 0.05)(B, S, D)),
            "w1": _w((lambda *s: torch.randn(*s, dtype=torch.bfloat16) * 0.8)(D, F) * (D ** -0.5)),
            "w2": _w((lambda *s: torch.randn(*s, dtype=torch.bfloat16) * 0.2)(F, D) * (F ** -0.5)),
        }
    _B_in = _B_setup()

    return {
        "A_x": _A_in["x"],
        "A_wqkv": _A_in["wqkv"],
        "A_wo": _A_in["wo"],
        "B_x": _B_in["x"],
        "B_w1": _B_in["w1"],
        "B_w2": _B_in["w2"],
    }

def reference(A_x, A_wqkv, A_wo, B_x, B_w1, B_w2):
    def _A_ref(x, wqkv, wo):
        B, S, D = x.shape
        H = 16; Dh = D // H
        qkv = (lambda x, *d: x.permute(*d))((x @ wqkv).reshape(B, S, 3, H, Dh), 2, 0, 3, 1, 4)
        q, k, v = qkv[0], qkv[1], qkv[2]
        scale = Dh ** -0.5
        scores = torch.einsum("bhqd,bhkd->bhqk", q, k) * scale
        p = _softmax(scores, axis=-1)
        o = torch.einsum("bhqk,bhkd->bhqd", p, v)
        return (lambda x, *d: x.permute(*d))(o, 0, 2, 1, 3).reshape(B, S, D) @ wo

    def _B_ref(x, w1, w2):
        h = torch.einsum("bsd,df->bsf", x, w1)
        h = _silu(h)
        out = torch.einsum("bsf,fd->bsd", h, w2)
        return out

    x = A_x
    h = x + _A_ref(_layernorm(x, axis=-1), A_wqkv, A_wo)
    h2 = h + _B_ref(_layernorm(h, axis=-1), B_w1, B_w2)
    return h2
```

```cpp
#include <cuda_runtime.h>
#include <cuda_bf16.h>
#include <cuda.h>
#include <stdint.h>

namespace {

constexpr int kS = 2048, kD = 448, kH = 16, kDH = 28, kF = 1792;
constexpr float kEps = 1e-5f;
constexpr float kQScale = 0.18898223650461362f * 1.4426950408889634f;

constexpr float kSafeBound = 56.f;
#define POLY_U 0x77
constexpr uint32_t kPolyU = POLY_U;

struct Scratch {
  unsigned char qkv[48 * 16 * 8192];
  unsigned char o[16 * 16 * 8192];
  __nv_bfloat16 h[kS * kD];
  uint4 part[16 * 8 * 4 * 4 * 256];
  float nrm[5 * 128 * 8];
  float2 st[16 * 8 * 128];
  unsigned cnt[4 * 16 * 32];
  unsigned ep[128];
};
__device__ __align__(1024) Scratch g_scr;

#define TM(i, cond)

#define MAPA 2
#define MAP 2
__device__ __forceinline__ void map_work(int b, int& ra, int& cb, int& rw, int& cw, int& rt, int& cs, int& head, int& qr) {
  const int k = b >> 1, r = b & 1;
  int grp, i;
  if (k < 4) { grp = 15; i = k; }
  else if (k < 36) { grp = (k - 4) & 7; i = (k - 4) >> 3; }
  else { i = (k - 36) / 7; grp = 8 + (k - 36) - 7 * i; }
  if (MAPA == 0) { ra = grp; cb = 2 * i + r; }
  else if (MAPA == 1) { ra = (grp >> 1) * 2 + (i >> 1); cb = ((grp & 1) * 2 + (i & 1)) * 2 + r; }
  else { ra = (grp & 3) * 4 + i; cb = (grp >> 2) * 2 + r; }
  rw = grp; cw = 2 * i + r;
  if (MAP == 0) { rt = grp; cs = 2 * i + r; }
  else if (MAP == 1) { rt = (grp >> 1) * 2 + (i >> 1); cs = ((grp & 1) * 2 + (i & 1)) * 2 + r; }
  else { rt = (grp & 3) * 4 + i; cs = (grp >> 2) * 2 + r; }
  head = grp; qr = 2 * i + r;
}

__device__ __forceinline__ uint32_t smem_u32(const void* p) {
  uint32_t a = (uint32_t)__cvta_generic_to_shared(p);
  asm volatile("mov.b32 %0, %0;" : "+r"(a));
  return a;
}
__device__ __forceinline__ bool elect_one() {
  uint32_t el;
  asm volatile("{.reg .pred p; elect.sync _|p, 0xffffffff; selp.u32 %0,1,0,p;}" : "=r"(el));
  return el != 0;
}
__device__ __forceinline__ void mbar_init(uint32_t a, uint32_t c) {
  asm volatile("mbarrier.init.shared::cta.b64 [%0], %1;" ::"r"(a), "r"(c) : "memory");
}
__device__ __forceinline__ void mbar_expect(uint32_t a, uint32_t b) {
  asm volatile("mbarrier.arrive.expect_tx.shared::cta.b64 _, [%0], %1;" ::"r"(a), "r"(b) : "memory");
}
__device__ __forceinline__ void mbar_arrive(uint32_t a) {
  asm volatile("mbarrier.arrive.shared::cta.b64 _, [%0];" ::"r"(a) : "memory");
}
__device__ __forceinline__ void mbar_wait(uint32_t a, uint32_t ph) {
  asm volatile(
      "{.reg .pred p; .reg .u32 c;\n"
      "mov.u32 c, 0;\n"
      "W%=: mbarrier.try_wait.parity.shared::cta.b64 p, [%0], %1;\n"
      "@p bra D%=;\n"
      "add.u32 c, c, 1;\n"
      "setp.lt.u32 p, c, 100000;\n"
      "@p bra W%=;\n"
      "D%=: }\n" ::"r"(a), "r"(ph) : "memory");
}
__device__ __forceinline__ void fence_init() { asm volatile("fence.mbarrier_init.release.cluster;" ::: "memory"); }
__device__ __forceinline__ void fence_async() { asm volatile("fence.proxy.async.shared::cta;" ::: "memory"); }
__device__ __forceinline__ void bar_sync(int id, int n) { asm volatile("bar.sync %0, %1;" ::"r"(id), "r"(n) : "memory"); }
__device__ __forceinline__ void bar_arrive(int id, int n) { asm volatile("bar.arrive %0, %1;" ::"r"(id), "r"(n) : "memory"); }
__device__ __forceinline__ void pdl_launch() { asm volatile("griddepcontrol.launch_dependents;"); }
__device__ __forceinline__ void pdl_wait() { asm volatile("griddepcontrol.wait;" ::: "memory"); }

__device__ __forceinline__ void tma_2d(uint32_t dst, const CUtensorMap* tm, uint32_t bar, int c0, int c1) {
  asm volatile("cp.async.bulk.tensor.2d.shared::cluster.global.mbarrier::complete_tx::bytes [%0], [%1, {%3, %4}], [%2];"
               ::"r"(dst), "l"(tm), "r"(bar), "r"(c0), "r"(c1) : "memory");
}
__device__ __forceinline__ void tma_2d_store(const CUtensorMap* tm, uint32_t src, int c0, int c1) {
  asm volatile("cp.async.bulk.tensor.2d.global.shared::cta.bulk_group [%0, {%2, %3}], [%1];"
               ::"l"(tm), "r"(src), "r"(c0), "r"(c1) : "memory");
}
__device__ __forceinline__ void bulk_ld(uint32_t dst, const void* src, uint32_t bytes, uint32_t bar) {
  asm volatile("cp.async.bulk.shared::cluster.global.mbarrier::complete_tx::bytes [%0], [%1], %2, [%3];"
               ::"r"(dst), "l"(src), "r"(bytes), "r"(bar) : "memory");
}
__device__ __forceinline__ void bulk_st(void* dst, uint32_t src, uint32_t bytes) {
  asm volatile("cp.async.bulk.global.shared::cta.bulk_group [%0], [%1], %2;" ::"l"(dst), "r"(src), "r"(bytes) : "memory");
}
__device__ __forceinline__ void bulk_commit_wait() {
  asm volatile("cp.async.bulk.commit_group;\ncp.async.bulk.wait_group 0;" ::: "memory");
}
__device__ __forceinline__ void l2_prefetch(const void* p, uint32_t bytes) {
  asm volatile("cp.async.bulk.prefetch.L2.global [%0], %1;" ::"l"(p), "r"(bytes) : "memory");
}
__device__ __forceinline__ void tmap_prefetch(const CUtensorMap* tm) {
  asm volatile("prefetch.tensormap [%0];" ::"l"(tm) : "memory");
}
__device__ __forceinline__ void ldsm4(uint32_t a, uint32_t& r0, uint32_t& r1, uint32_t& r2, uint32_t& r3) {
  asm volatile("ldmatrix.sync.aligned.m8n8.x4.shared.b16 {%0,%1,%2,%3}, [%4];"
               : "=r"(r0), "=r"(r1), "=r"(r2), "=r"(r3) : "r"(a) : "memory");
}
__device__ __forceinline__ void stsm4(uint32_t a, uint32_t r0, uint32_t r1, uint32_t r2, uint32_t r3) {
  asm volatile("stmatrix.sync.aligned.m8n8.x4.shared.b16 [%0], {%1,%2,%3,%4};"
               ::"r"(a), "r"(r0), "r"(r1), "r"(r2), "r"(r3) : "memory");
}
__device__ __forceinline__ void stsm2(uint32_t a, uint32_t r0, uint32_t r1) {
  asm volatile("stmatrix.sync.aligned.m8n8.x2.shared.b16 [%0], {%1,%2};" ::"r"(a), "r"(r0), "r"(r1) : "memory");
}
__device__ __forceinline__ void sts32(uint32_t a, uint32_t v) { asm volatile("st.shared.b32 [%0], %1;" ::"r"(a), "r"(v) : "memory"); }
__device__ __forceinline__ void sts64(uint32_t a, uint32_t x, uint32_t y) {
  asm volatile("st.shared.v2.b32 [%0], {%1,%2};" ::"r"(a), "r"(x), "r"(y) : "memory");
}
__device__ __forceinline__ void sts128z(uint32_t a) {
  asm volatile("st.shared.v4.b32 [%0], {%1,%1,%1,%1};" ::"r"(a), "r"(0u) : "memory");
}
__device__ __forceinline__ void hmma(float* d, uint32_t a0, uint32_t a1, uint32_t a2, uint32_t a3, uint32_t b0, uint32_t b1) {
  asm volatile("mma.sync.aligned.m16n8k16.row.col.f32.bf16.bf16.f32 {%0,%1,%2,%3},{%4,%5,%6,%7},{%8,%9},{%0,%1,%2,%3};"
               : "+f"(d[0]), "+f"(d[1]), "+f"(d[2]), "+f"(d[3]) : "r"(a0), "r"(a1), "r"(a2), "r"(a3), "r"(b0), "r"(b1));
}
__device__ __forceinline__ uint32_t pack2(float lo, float hi) {
  uint32_t r;
  asm("cvt.rn.bf16x2.f32 %0, %1, %2;" : "=r"(r) : "f"(hi), "f"(lo));
  return r;
}
__device__ __forceinline__ float bf_lo(uint32_t v) { return __uint_as_float(v << 16); }
__device__ __forceinline__ float bf_hi(uint32_t v) { return __uint_as_float(v & 0xFFFF0000u); }
__device__ __forceinline__ uint32_t hsub2(uint32_t a, uint32_t b) {
  uint32_t r;
  asm("sub.rn.bf16x2 %0, %1, %2;" : "=r"(r) : "r"(a), "r"(b));
  return r;
}
__device__ __forceinline__ uint32_t hfma2(uint32_t a, uint32_t b, uint32_t c) {
  uint32_t r;
  asm("fma.rn.bf16x2 %0, %1, %2, %3;" : "=r"(r) : "r"(a), "r"(b), "r"(c));
  return r;
}
__device__ __forceinline__ uint32_t hadd2(uint32_t a, uint32_t b) {
  uint32_t r;
  asm("add.rn.bf16x2 %0, %1, %2;" : "=r"(r) : "r"(a), "r"(b));
  return r;
}
__device__ __forceinline__ float ex2(float x) { float y; asm("ex2.approx.ftz.f32 %0, %1;" : "=f"(y) : "f"(x)); return y; }
__device__ __forceinline__ float rcp_fast(float x) { float y; asm("rcp.approx.ftz.f32 %0, %1;" : "=f"(y) : "f"(x)); return y; }
__device__ __forceinline__ float tanh_fast(float x) { float y; asm("tanh.approx.f32 %0, %1;" : "=f"(y) : "f"(x)); return y; }

__device__ __forceinline__ uint64_t mkdesc(uint32_t addr, uint32_t lbo, uint32_t sbo, uint32_t mode) {
  uint32_t lo = ((addr & 0x3FFFF) >> 4) | ((lbo >> 4) << 16);
  asm("mov.b32 %0, %0;" : "+r"(lo));
  return (uint64_t)lo | ((uint64_t)(sbo >> 4) << 32) | ((uint64_t)mode << 62);
}
__device__ __forceinline__ uint64_t dadd(uint64_t d, uint32_t bytes) {
  return (d & 0xFFFFFFFF00000000ull) | (uint32_t)((uint32_t)d + (bytes >> 4));
}
__device__ __forceinline__ void wg_fence() { asm volatile("wgmma.fence.sync.aligned;" ::: "memory"); }
__device__ __forceinline__ void wg_commit() { asm volatile("wgmma.commit_group.sync.aligned;" ::: "memory"); }
template <int N> __device__ __forceinline__ void wg_wait() { asm volatile("wgmma.wait_group.sync.aligned %0;" ::"n"(N) : "memory"); }
template <int N> __device__ __forceinline__ void keep(float (&d)[N]) {
#pragma unroll
  for (int i = 0; i < N; i++) asm volatile("" : "+f"(d[i])::"memory");
}
template <int N> __device__ __forceinline__ void keep(uint32_t (&d)[N]) {
#pragma unroll
  for (int i = 0; i < N; i++) asm volatile("" : "+r"(d[i])::"memory");
}
template <int R> __device__ __forceinline__ void reg_inc() { asm volatile("setmaxnreg.inc.sync.aligned.u32 %0;" ::"n"(R)); }
template <int R> __device__ __forceinline__ void reg_dec() { asm volatile("setmaxnreg.dec.sync.aligned.u32 %0;" ::"n"(R)); }

__device__ __forceinline__ void tma_3d(uint32_t dst, const CUtensorMap* tm, uint32_t bar, int c0, int c1, int c2) {
  asm volatile("cp.async.bulk.tensor.3d.shared::cluster.global.mbarrier::complete_tx::bytes [%0], [%1, {%3, %4, %5}], [%2];"
               ::"r"(dst), "l"(tm), "r"(bar), "r"(c0), "r"(c1), "r"(c2) : "memory");
}
__device__ __forceinline__ void bulk_commit() { asm volatile("cp.async.bulk.commit_group;" ::: "memory"); }
__device__ __forceinline__ void bulk_wait() { asm volatile("cp.async.bulk.wait_group 0;" ::: "memory"); }
__device__ __forceinline__ void signal(unsigned* p) { asm volatile("red.relaxed.gpu.global.add.u32 [%0], 1;" ::"l"(p) : "memory"); }
__device__ __forceinline__ void fence_gpu() { asm volatile("fence.acq_rel.gpu;" ::: "memory"); }
__device__ __forceinline__ unsigned ld_relaxed(const unsigned* p) {
  unsigned v; asm volatile("ld.relaxed.gpu.global.u32 %0, [%1];" : "=r"(v) : "l"(p) : "memory"); return v;
}
__device__ __forceinline__ void poll(const unsigned* p, unsigned target) {
  for (int it = 0; it < 200000; it++)
    if (__all_sync(~0u, (int)(ld_relaxed(p) - target) >= 0)) break;
  asm volatile("fence.proxy.async.global;" ::: "memory");
}
__device__ __forceinline__ ptrdiff_t blob_off(int s, int rt) {
  return s < 16 ? (ptrdiff_t)(s * 16 + rt) * 8192 : (ptrdiff_t)(256 + (((s & 15) * 16 + rt) * 2 + (s >> 5))) * 8192;
}
__device__ __forceinline__ uint32_t lds32(uint32_t a) { uint32_t v; asm volatile("ld.shared.b32 %0, [%1];" : "=r"(v) : "r"(a) : "memory"); return v; }
__device__ __forceinline__ uint2 lds64(uint32_t a) { uint2 v; asm volatile("ld.shared.v2.b32 {%0,%1}, [%2];" : "=r"(v.x), "=r"(v.y) : "r"(a) : "memory"); return v; }
__device__ __forceinline__ float4 lds128(uint32_t a) {
  float4 v; asm volatile("ld.shared.v4.f32 {%0,%1,%2,%3}, [%4];" : "=f"(v.x), "=f"(v.y), "=f"(v.z), "=f"(v.w) : "r"(a) : "memory"); return v;
}
__device__ __forceinline__ void sts128(uint32_t a, float x, float y, float z, float w) {
  asm volatile("st.shared.v4.f32 [%0], {%1,%2,%3,%4};" ::"r"(a), "f"(x), "f"(y), "f"(z), "f"(w) : "memory");
}
__device__ __forceinline__ uint32_t peer_addr(uint32_t a, uint32_t rank) {
  uint32_t r; asm("mapa.shared::cluster.u32 %0, %1, %2;" : "=r"(r) : "r"(a), "r"(rank)); return r;
}
__device__ __forceinline__ void mbar_arrive_peer(uint32_t a) {
  asm volatile("mbarrier.arrive.relaxed.cluster.shared::cluster.b64 _, [%0];" ::"r"(a) : "memory");
}
__device__ __forceinline__ void st_async(uint32_t a, uint32_t x, uint32_t y, uint32_t z, uint32_t w, uint32_t bar) {
  asm volatile("st.async.weak.shared::cluster.mbarrier::complete_tx::bytes.v4.b32 [%0], {%1,%2,%3,%4}, [%5];"
               ::"r"(a), "r"(x), "r"(y), "r"(z), "r"(w), "r"(bar) : "memory");
}
__device__ __forceinline__ void bulk_to_peer(uint32_t dst, uint32_t src, uint32_t bytes, uint32_t bar) {
  asm volatile("cp.async.bulk.shared::cluster.shared::cta.mbarrier::complete_tx::bytes [%0], [%1], %2, [%3];"
               ::"r"(dst), "r"(src), "r"(bytes), "r"(bar) : "memory");
}
__device__ __forceinline__ void sts128u(uint32_t a, uint32_t x, uint32_t y, uint32_t z, uint32_t w) {
  asm volatile("st.shared.v4.b32 [%0], {%1,%2,%3,%4};" ::"r"(a), "r"(x), "r"(y), "r"(z), "r"(w) : "memory");
}
__device__ __forceinline__ void lds128u(uint32_t a, uint32_t* v) {
  asm volatile("ld.shared.v4.b32 {%0,%1,%2,%3}, [%4];" : "=r"(v[0]), "=r"(v[1]), "=r"(v[2]), "=r"(v[3]) : "r"(a) : "memory");
}
__device__ __forceinline__ void ld_pkt(const uint4* p, uint32_t* r) {
  asm volatile("{.reg .b128 v; ld.relaxed.gpu.global.b128 v, [%4]; mov.b128 {%0,%1,%2,%3}, v;}"
               : "=r"(r[0]), "=r"(r[1]), "=r"(r[2]), "=r"(r[3]) : "l"(p) : "memory");
}

template<int SC, int SA = 1> __device__ __forceinline__ void wgmma_rs_n192_tb(float* d, uint32_t a0, uint32_t a1, uint32_t a2, uint32_t a3, uint64_t db) {
  asm volatile("{.reg .pred p; setp.ne.b32 p, %101, 0;\n"
    "wgmma.mma_async.sync.aligned.m64n192k16.f32.bf16.bf16 {%0,%1,%2,%3,%4,%5,%6,%7,%8,%9,%10,%11,%12,%13,%14,%15,%16,%17,%18,%19,%20,%21,%22,%23,%24,%25,%26,%27,%28,%29,%30,%31,%32,%33,%34,%35,%36,%37,%38,%39,%40,%41,%42,%43,%44,%45,%46,%47,%48,%49,%50,%51,%52,%53,%54,%55,%56,%57,%58,%59,%60,%61,%62,%63,%64,%65,%66,%67,%68,%69,%70,%71,%72,%73,%74,%75,%76,%77,%78,%79,%80,%81,%82,%83,%84,%85,%86,%87,%88,%89,%90,%91,%92,%93,%94,%95}, {%96,%97,%98,%99}, %100, p, %102, 1, 1;}\n"
    : "+f"(d[0]), "+f"(d[1]), "+f"(d[2]), "+f"(d[3]), "+f"(d[4]), "+f"(d[5]), "+f"(d[6]), "+f"(d[7]), "+f"(d[8]), "+f"(d[9]), "+f"(d[10]), "+f"(d[11]), "+f"(d[12]), "+f"(d[13]), "+f"(d[14]), "+f"(d[15]), "+f"(d[16]), "+f"(d[17]), "+f"(d[18]), "+f"(d[19]), "+f"(d[20]), "+f"(d[21]), "+f"(d[22]), "+f"(d[23]), "+f"(d[24]), "+f"(d[25]), "+f"(d[26]), "+f"(d[27]), "+f"(d[28]), "+f"(d[29]), "+f"(d[30]), "+f"(d[31]), "+f"(d[32]), "+f"(d[33]), "+f"(d[34]), "+f"(d[35]), "+f"(d[36]), "+f"(d[37]), "+f"(d[38]), "+f"(d[39]), "+f"(d[40]), "+f"(d[41]), "+f"(d[42]), "+f"(d[43]), "+f"(d[44]), "+f"(d[45]), "+f"(d[46]), "+f"(d[47]), "+f"(d[48]), "+f"(d[49]), "+f"(d[50]), "+f"(d[51]), "+f"(d[52]), "+f"(d[53]), "+f"(d[54]), "+f"(d[55]), "+f"(d[56]), "+f"(d[57]), "+f"(d[58]), "+f"(d[59]), "+f"(d[60]), "+f"(d[61]), "+f"(d[62]), "+f"(d[63]), "+f"(d[64]), "+f"(d[65]), "+f"(d[66]), "+f"(d[67]), "+f"(d[68]), "+f"(d[69]), "+f"(d[70]), "+f"(d[71]), "+f"(d[72]), "+f"(d[73]), "+f"(d[74]), "+f"(d[75]), "+f"(d[76]), "+f"(d[77]), "+f"(d[78]), "+f"(d[79]), "+f"(d[80]), "+f"(d[81]), "+f"(d[82]), "+f"(d[83]), "+f"(d[84]), "+f"(d[85]), "+f"(d[86]), "+f"(d[87]), "+f"(d[88]), "+f"(d[89]), "+f"(d[90]), "+f"(d[91]), "+f"(d[92]), "+f"(d[93]), "+f"(d[94]), "+f"(d[95])
    : "r"(a0), "r"(a1), "r"(a2), "r"(a3), "l"(db), "n"(SC), "n"(SA));
}
template<int SC, int SA = 1> __device__ __forceinline__ void wgmma_rs_n32_tb(float* d, uint32_t a0, uint32_t a1, uint32_t a2, uint32_t a3, uint64_t db) {
  asm volatile("{.reg .pred p; setp.ne.b32 p, %21, 0;\n"
    "wgmma.mma_async.sync.aligned.m64n32k16.f32.bf16.bf16 {%0,%1,%2,%3,%4,%5,%6,%7,%8,%9,%10,%11,%12,%13,%14,%15}, {%16,%17,%18,%19}, %20, p, %22, 1, 1;}\n"
    : "+f"(d[0]), "+f"(d[1]), "+f"(d[2]), "+f"(d[3]), "+f"(d[4]), "+f"(d[5]), "+f"(d[6]), "+f"(d[7]), "+f"(d[8]), "+f"(d[9]), "+f"(d[10]), "+f"(d[11]), "+f"(d[12]), "+f"(d[13]), "+f"(d[14]), "+f"(d[15])
    : "r"(a0), "r"(a1), "r"(a2), "r"(a3), "l"(db), "n"(SC), "n"(SA));
}
template<int SC, int SA = 1> __device__ __forceinline__ void wgmma_rs_n64(float* d, uint32_t a0, uint32_t a1, uint32_t a2, uint32_t a3, uint64_t db) {
  asm volatile("{.reg .pred p; setp.ne.b32 p, %37, 0;\n"
    "wgmma.mma_async.sync.aligned.m64n64k16.f32.bf16.bf16 {%0,%1,%2,%3,%4,%5,%6,%7,%8,%9,%10,%11,%12,%13,%14,%15,%16,%17,%18,%19,%20,%21,%22,%23,%24,%25,%26,%27,%28,%29,%30,%31}, {%32,%33,%34,%35}, %36, p, %38, 1, 0;}\n"
    : "+f"(d[0]), "+f"(d[1]), "+f"(d[2]), "+f"(d[3]), "+f"(d[4]), "+f"(d[5]), "+f"(d[6]), "+f"(d[7]), "+f"(d[8]), "+f"(d[9]), "+f"(d[10]), "+f"(d[11]), "+f"(d[12]), "+f"(d[13]), "+f"(d[14]), "+f"(d[15]), "+f"(d[16]), "+f"(d[17]), "+f"(d[18]), "+f"(d[19]), "+f"(d[20]), "+f"(d[21]), "+f"(d[22]), "+f"(d[23]), "+f"(d[24]), "+f"(d[25]), "+f"(d[26]), "+f"(d[27]), "+f"(d[28]), "+f"(d[29]), "+f"(d[30]), "+f"(d[31])
    : "r"(a0), "r"(a1), "r"(a2), "r"(a3), "l"(db), "n"(SC), "n"(SA));
}
template<int SC, int SA = 1> __device__ __forceinline__ void wgmma_rs_n64_tb(float* d, uint32_t a0, uint32_t a1, uint32_t a2, uint32_t a3, uint64_t db) {
  asm volatile("{.reg .pred p; setp.ne.b32 p, %37, 0;\n"
    "wgmma.mma_async.sync.aligned.m64n64k16.f32.bf16.bf16 {%0,%1,%2,%3,%4,%5,%6,%7,%8,%9,%10,%11,%12,%13,%14,%15,%16,%17,%18,%19,%20,%21,%22,%23,%24,%25,%26,%27,%28,%29,%30,%31}, {%32,%33,%34,%35}, %36, p, %38, 1, 1;}\n"
    : "+f"(d[0]), "+f"(d[1]), "+f"(d[2]), "+f"(d[3]), "+f"(d[4]), "+f"(d[5]), "+f"(d[6]), "+f"(d[7]), "+f"(d[8]), "+f"(d[9]), "+f"(d[10]), "+f"(d[11]), "+f"(d[12]), "+f"(d[13]), "+f"(d[14]), "+f"(d[15]), "+f"(d[16]), "+f"(d[17]), "+f"(d[18]), "+f"(d[19]), "+f"(d[20]), "+f"(d[21]), "+f"(d[22]), "+f"(d[23]), "+f"(d[24]), "+f"(d[25]), "+f"(d[26]), "+f"(d[27]), "+f"(d[28]), "+f"(d[29]), "+f"(d[30]), "+f"(d[31])
    : "r"(a0), "r"(a1), "r"(a2), "r"(a3), "l"(db), "n"(SC), "n"(SA));
}
template<int SC> __device__ __forceinline__ void wgmma_ss_n64_tb(float* d, uint64_t da, uint64_t db) {
  asm volatile("{.reg .pred p; setp.ne.b32 p, %34, 0;\n"
    "wgmma.mma_async.sync.aligned.m64n64k16.f32.bf16.bf16 {%0,%1,%2,%3,%4,%5,%6,%7,%8,%9,%10,%11,%12,%13,%14,%15,%16,%17,%18,%19,%20,%21,%22,%23,%24,%25,%26,%27,%28,%29,%30,%31}, %32, %33, p, 1, 1, 0, 1;}\n"
    : "+f"(d[0]), "+f"(d[1]), "+f"(d[2]), "+f"(d[3]), "+f"(d[4]), "+f"(d[5]), "+f"(d[6]), "+f"(d[7]), "+f"(d[8]), "+f"(d[9]), "+f"(d[10]), "+f"(d[11]), "+f"(d[12]), "+f"(d[13]), "+f"(d[14]), "+f"(d[15]), "+f"(d[16]), "+f"(d[17]), "+f"(d[18]), "+f"(d[19]), "+f"(d[20]), "+f"(d[21]), "+f"(d[22]), "+f"(d[23]), "+f"(d[24]), "+f"(d[25]), "+f"(d[26]), "+f"(d[27]), "+f"(d[28]), "+f"(d[29]), "+f"(d[30]), "+f"(d[31])
    : "l"(da), "l"(db), "n"(SC));
}

constexpr int SLOT = 32768;
constexpr int A_W = 57344;
constexpr int A_X = 2 * A_W;
constexpr int A_STG = 3 * A_W;
constexpr int B_Q = 2 * SLOT, B_KV = B_Q + 16384;
constexpr int NS = 6;
#define PF 1
#define NPRE 1
#define ALIGN 0
#define EXP 0
#define PBW 1
#define WB 0
#define C1D 5
#define SFEN 0
#define FWD 0
#define PACE0 2
constexpr int U = 16384;
constexpr int C_O = 4 * U;
constexpr int C_STG = 11 * U;
constexpr int BAR = 7 * SLOT;
constexpr int AUX_EP = BAR + 1408, AUX_OQ = BAR + 1440, AUX_KM = BAR + 1536, AUX_NR = BAR + 2560;
constexpr int SMEM = BAR + 2816;
enum { XF = 0, WF = 7, XFREE = 14, W2P = 15, SQF = 19, ASTG = 20, PST = 21, QF = 33, KVF = 34, KVE = 40, WOF = 46,
       BDONE = 47, OF = 48, CMMA = 64, STF = 65, HF = 66, HREL = 73, W1F = 80, W1REL = 94, W2F = 108, W2REL = 115, HAND = 122,
       XRF = 130, XRD = 131, CRED = 132, INB = 133, RESD = 141, HST = 149, DUMMY = 150, KVD = 151, BD1 = 152, NBAR = 153 };
__host__ __device__ constexpr int bar_count(int i) {
  return i == ASTG ? 14 : (i >= W1F && i < W1F + 7) ? 2 : i == DUMMY ? 1000 : i == HST ? 8 : (i >= PST && i <= QF) ? 2
       : (i == KVD || (i >= KVE && i < WOF)) ? 16
       : (i == BDONE || i == BD1 || i == XFREE || i == CMMA || i == XRD || i == CRED || (i >= HREL && i < W1F) || (i >= W1REL && i < W2F) || (i >= W2REL && i < HAND)) ? 8 : 1;
}
__host__ __device__ constexpr int w1_off(int i) { constexpr int u[7] = {12, 0, 2, 4, 12, 0, 6}; return u[i] * U; }
__host__ __device__ constexpr int w2_off(int i) { constexpr int u[7] = {8, 10, 4, 12, 6, 8, 10}; return u[i] * U; }
constexpr int C_XR = 13 * U;
constexpr int C_IN = 0;
constexpr int C_HAND = 4 * U, C_OUT = 12 * U;

struct PolyC { uint32_t one, a, b, c; };
__device__ __forceinline__ uint32_t exp2_pair(float x0, float x1, const PolyC& k) {
  const uint32_t w = __byte_perm(__float_as_uint(x0), __float_as_uint(x1), 0x6521);
  uint32_t z, d, p;
  asm("lop3.b32 %0, %1, 0x007F007F, %2, 0xEA;" : "=r"(z) : "r"(w), "r"(k.one));
  asm("fma.rn.bf16x2 %0, %1, %2, %3;" : "=r"(d) : "r"(z), "r"(k.a), "r"(k.b));
  asm("fma.rn.bf16x2 %0, %1, %1, %2;" : "=r"(p) : "r"(d), "r"(k.c));
  return p + w;
}

#define LANE_VARS                                                                                         \
  int tid;                                                                                                \
  asm volatile("mov.u32 %0, %%tid.x;" : "=r"(tid));                                                       \
  [[maybe_unused]] const int lane = tid & 31, g = lane >> 2, c = lane & 3;                                 \
  [[maybe_unused]] const int lr = (lane & 7) + ((lane >> 3) & 1) * 8, hi = lane >> 4;

struct Params {
  CUtensorMap x, wa, wb, wo, w1, w2, h, hst, out;
  const __nv_bfloat16 *xp, *wqp, *wop, *w1p, *w2p;
  Scratch* scr;
};

__global__ void __cluster_dims__(2, 1, 1) __launch_bounds__(512, 1) k_block(const __grid_constant__ Params P) {
  extern __shared__ __align__(1024) unsigned char smem[];
  const uint32_t sb = smem_u32(smem), bar = sb + BAR;
  const int warp = __shfl_sync(~0u, threadIdx.x >> 5, 0), wg = warp >> 2;
  const int b = blockIdx.x;
  int ra, cb, rw, cw, rt, cs, head, qr;
  map_work(b, ra, cb, rw, cw, rt, cs, head, qr);
  Scratch* const scr = P.scr;
  TM(0, threadIdx.x == 0);

  {
    const int t = threadIdx.x;
    if (t < 128 && cb < 7) asm volatile("prefetch.global.L2 [%0];" ::"l"((const char*)P.xp + ra * 114688 + cb * 16384 + t * 128));
    if (PF > 1 && t >= 128 && t < 128 + 74 && b * 74 + t - 128 < 9408) asm volatile("prefetch.global.L2 [%0];" ::"l"((const char*)P.wqp + (b * 74 + t - 128) * 128));
  }
  if (wg >= 2) {
    reg_dec<40>();
    LANE_VARS
    const bool el = elect_one();
    if (warp == 8) {
      if (el) {
#pragma unroll
        for (int i = 0; i < 7; i++) mbar_init(bar + 8 * (XF + i), 1);
        fence_init();
        if (cb < 7) {
#pragma unroll
          for (int i = 0; i < 7; i++) { mbar_expect(bar + 8 * (XF + i), 16384); tma_2d(sb + A_X + i * 16384, &P.x, bar + 8 * (XF + i), i * 64, ra * 128); }
        }
#pragma unroll
        for (int i = 0; i < 7; i++) mbar_init(bar + 8 * (WF + i), 1);
        fence_init();
      }
      __syncwarp();
      bar_arrive(1, 512);
      if (cb < 7 && el) {
#pragma unroll
        for (int i = 0; i < 7; i++) { mbar_expect(bar + 8 * (WF + i), 8192); tma_2d(sb + i * 8192, &P.wa, bar + 8 * (WF + i), cb * 192, i * 64); }
      }
      __syncwarp();
      bar_sync(2, 96);
      if (cb < 7 && el) {
#pragma unroll
        for (int i = 0; i < 2; i++) { mbar_expect(bar + 8 * (W2P + i), 28672); tma_2d(sb + A_W + i * 28672, &P.wb, bar + 8 * (W2P + i), cb * 192 + 128, i * 224); }
      }
      __syncwarp();
    } else {
      if (warp == 12) {
        if (el) {
#pragma unroll
          for (int i = 14; i < NBAR; i++) mbar_init(bar + 8 * i, bar_count(i));
          fence_init();
        }
        __syncwarp();
        bar_arrive(2, 96);
      }
      bar_sync(1, 512);
      if (warp == 9) {
        if (el) {
          const unsigned ep = __ldcg(&scr->ep[b]) + 1;
          tmap_prefetch(&P.wo); tmap_prefetch(&P.w1); tmap_prefetch(&P.w2); tmap_prefetch(&P.h); tmap_prefetch(&P.hst); tmap_prefetch(&P.out);
          scr->ep[b] = ep;
          sts32(sb + AUX_EP, ep);
          sts64(sb + AUX_EP + 8, 0x3F803F80u, 0x26122612u);
          sts32(sb + AUX_EP + 16, (ep & 1u) | ((ep & 2u) << 15));
#pragma unroll
          for (int i = 0; i < 8; i++) { mbar_expect(bar + 8 * (INB + i), 8192); mbar_expect(bar + 8 * (OF + i), 16384); }
        }
        __syncwarp();
        bar_arrive(2, 96);
      }
    }
    if (warp == 8) {
      const unsigned ep = __shfl_sync(~0u, lds32(sb + AUX_EP), 0);
      if (cb < 7) {
        mbar_wait(bar + 8 * XFREE, 0);
        if (el) {
#pragma unroll
          for (int i = 2; i < 4; i++) { mbar_expect(bar + 8 * (W2P + i), 28672); tma_2d(sb + A_W + i * 28672, &P.wb, bar + 8 * (W2P + i), cb * 192 + 64, (i & 1) * 224); }
        }
      }
      poll(&scr->cnt[(lane & 15) * 32], 7 * ep);
      TM(8, lane == 0);
      if (el) {
        mbar_expect(bar + 8 * QF, 16384);
        bulk_ld(sb + B_Q, scr->qkv + blob_off(head, 2 * qr), 16384, bar + 8 * QF);
        mbar_expect(bar + 8 * KVF, 16384);
        bulk_ld(sb + B_KV, scr->qkv + blob_off(16 + head, 0), 16384, bar + 8 * KVF);
      }
      {
        const int cq = (28 * head) / 192, lq = head + 1 - 7 * cq, ck = (448 + 28 * head) / 192, lk = head + 17 - 7 * ck;
        const unsigned* nq = reinterpret_cast<const unsigned*>(scr->nrm) + (cq * 128 + qr * 16 + (lane & 15)) * 8;
        const unsigned* nk = reinterpret_cast<const unsigned*>(scr->nrm) + (ck * 128 + lane) * 8;
        const unsigned q0 = __ldcg(nq + lq), q1 = lq == 7 ? __ldcg(nq + 1024) : 0u;
        unsigned k0 = 0, k1 = 0;
#pragma unroll
        for (int i = 0; i < 4; i++) {
          k0 = max(k0, __ldcg(nk + i * 256 + lk));
          if (lk == 7) k1 = max(k1, __ldcg(nk + i * 256 + 1024));
        }
        const float km = __uint_as_float(__reduce_max_sync(~0u, k0)) + __uint_as_float(__reduce_max_sync(~0u, k1));
        const bool ok = (__uint_as_float(q0) + __uint_as_float(q1)) * km <= kSafeBound * kSafeBound;
        const unsigned okm = __ballot_sync(~0u, ok);
        if (el) { sts32(sb + AUX_EP + 4, okm); mbar_arrive(bar + 8 * QF); }
      }
      if (el) {
#pragma unroll
        for (int s = 1; s < NS; s++) {
          mbar_expect(bar + 8 * (KVF + s), 16384);
          bulk_ld(sb + B_KV + s * 16384, scr->qkv + blob_off(16 + head, s), 16384, bar + 8 * (KVF + s));
        }
      }
      __syncwarp();
    } else if (warp == 9) {
      if (cb < 7) { mbar_wait(bar + 8 * ASTG, 0); if (el) signal(&scr->cnt[ra * 32]); }
      __syncwarp();
    } else if (wg == 3 && cb < 7) {
      const int n0 = (23 - cb) / 7, n2 = (45 - cb) / 7;
#pragma unroll 1
      for (int p = 0; p < 3; p++) {
        const int lo = p == 0 ? 1 : (p == 1 ? n2 : n0), hi2 = p == 0 ? n0 : (p == 1 ? 7 : n2);
        mbar_wait(bar + 8 * (PST + p * 4 + (warp - 12)), 0);
        TM(49 + 2 * p, tid == 384);
        if (el) {
#pragma unroll
          for (int i = 0; i < 4; i++)
            if (lo + i < hi2) bulk_st(scr->qkv + blob_off(7 * cb - 1 + lo + i, ra) + (warp - 12) * 2048, sb + A_STG + (lo + i) * 8192 + (warp - 12) * 2048, 2048);
        }
        __syncwarp();
      }
      if (el) {
        bulk_commit(); bulk_wait();
        mbar_arrive(bar + 8 * ASTG);
      }
      __syncwarp();
      TM(55, tid == 384);
    } else if (warp >= 10 && cb < 7) {
#pragma unroll 1
      for (int p = 0; p < 2; p++) {
        const int u = lane & 7, e = p == 0 ? 7 - cb + u : u, r0 = (warp - 10) * 64 + (lane >> 3);
        const bool on = p == 0 ? (cb > 0 && u <= cb) : u < 6 - cb;
        const uint32_t o0 = r0 * 64 + (((e >> 1) ^ (r0 >> 1 & 1)) << 4) + (e & 1) * 8, o1 = (o0 ^ 32) + 256;
        unsigned char* const blob = scr->qkv + blob_off(7 * cb - 1 + 7 * p, ra);
        mbar_wait(bar + 8 * (PST + p * 4 + (warp - 10) * 2), 0); mbar_wait(bar + 8 * (PST + p * 4 + (warp - 10) * 2 + 1), 0);
        if (on) {
#pragma unroll
          for (int it = 0; it < 8; it++) {
            *reinterpret_cast<uint2*>(blob + o0 + it * 512) = lds64(sb + A_STG + o0 + it * 512);
            *reinterpret_cast<uint2*>(blob + o1 + it * 512) = lds64(sb + A_STG + o1 + it * 512);
          }
        }
      }
      fence_gpu();
      __syncwarp();
      if (el) mbar_arrive(bar + 8 * ASTG);
      TM(54, tid == 320);
    }
    reg_inc<128>();
  } else {
    reg_inc<216>();
    LANE_VARS
    bar_sync(1, 512);
    if (cb < 7) {
      uint32_t a[112];
      float mu0, mu1, rs0, rs1, q[4] = {0, 0, 0, 0};
      auto squares = [&](const uint32_t* p, float (&q)[4]) {
#pragma unroll
        for (int i = 0; i < 16; i++) { q[i & 1] = fmaf(bf_lo(p[i]), bf_lo(p[i]), q[i & 1]); q[2 + (i & 1)] = fmaf(bf_hi(p[i]), bf_hi(p[i]), q[2 + (i & 1)]); }
        keep(q);
      };
      {
        const uint32_t xb = sb + A_X + (warp * 16 + lr) * 128, xsw = lr & 7;
        float s1[4] = {0, 0, 0, 0}, s2[4] = {0, 0, 0, 0};
#pragma unroll
        for (int kb = 0; kb < 8; kb++) {
          if (kb < 7) {
            uint32_t* p = &a[16 * (kb < 7 ? kb : 0)];
            mbar_wait(bar + 8 * (XF + kb), 0);
            if (kb == 0) TM(1, tid == 0);
            if (kb == 6) TM(2, tid == 0);
#pragma unroll
            for (int t = 0; t < 4; t++) ldsm4(xb + kb * 16384 + (((2 * t + hi) ^ xsw) << 4), p[4 * t], p[4 * t + 1], p[4 * t + 2], p[4 * t + 3]);
          }
          if (kb > 0) {
            const uint32_t* p = &a[16 * (kb > 0 ? kb - 1 : 0)];
#pragma unroll
            for (int t = 0; t < 4; t++) hmma((t & 1) ? s2 : s1, p[4 * t], p[4 * t + 1], p[4 * t + 2], p[4 * t + 3], 0x3F803F80u, 0x3F803F80u);
            if (kb < 7) squares(p, q);
          }
        }
        if (lane == 0) mbar_arrive(bar + 8 * XFREE);
        mu0 = (s1[0] + s2[0]) * (1.f / kD); mu1 = (s1[2] + s2[2]) * (1.f / kD);
      }
      TM(3, tid == 0);
      const uint64_t dw = mkdesc(sb, 1024, 1024, 1);
      float acc[2][32];
      {
        const uint32_t m0 = pack2(mu0, mu0), m1 = pack2(mu1, mu1);
#pragma unroll
        for (int i = 0; i < 16; i++) a[i] = hsub2(a[i], (i & 1) ? m1 : m0);
#pragma unroll
        for (int kb = 0; kb < 7; kb++) {
          mbar_wait(bar + 8 * (WF + kb), 0);
          wg_fence();
#pragma unroll
          for (int t = 4 * kb; t < 4 * kb + 4; t++) {
            if (t == 0) wgmma_rs_n64_tb<0>(acc[0], a[0], a[1], a[2], a[3], dw);
            else wgmma_rs_n64_tb<1>(acc[0], a[4 * t], a[4 * t + 1], a[4 * t + 2], a[4 * t + 3], dadd(dw, t * 2048));
            if (t == 1) { squares(&a[96], q); rs0 = q[0] + q[2]; rs1 = q[1] + q[3]; }
            if (t < 24) {
#pragma unroll
              for (int i = 4 * t + 16; i < 4 * t + 20; i++) { a[i] = hsub2(a[i], (i & 1) ? m1 : m0); asm volatile("" : "+r"(a[i])::"memory"); }
            }
          }
        }
        wg_commit();
      }
      const bool el = elect_one();
      uint32_t ad[7];
#pragma unroll
      for (int p = 0; p < 3; p++) {
        float(&d)[32] = acc[p & 1];
        float(&e)[32] = acc[(p + 1) & 1];
        const uint64_t db = dadd(dw, (p + 1) * A_W);
        if (p < 2) {
          mbar_wait(bar + 8 * (W2P + 2 * p), 0); mbar_wait(bar + 8 * (W2P + 2 * p + 1), 0);
          if (p == 0) mbar_wait(bar + 8 * XFREE, 0);
          wg_fence();
          wgmma_rs_n64_tb<0>(e, a[0], a[1], a[2], a[3], db);
          wgmma_rs_n64_tb<1>(e, a[4], a[5], a[6], a[7], dadd(db, 2048));
          if (p == 0) {
            const int row = warp * 16 + g;
            const uint32_t sw = (row >> 1) & 3, rb = sb + A_STG + row * 64 + (c & 1) * 4;
#pragma unroll
            for (int j = 0; j < 7; j++) {
              const int lu = 2 * j + (c >> 1) + 7 - cb, ls = (lu >= 7) + (lu >= 14), u4 = lu - 7 * ls;
              ad[j] = rb + ls * 8192 + (((u4 >> 1) ^ sw) << 4) + (u4 & 1) * 8;
              ad[j] = __shfl_sync(~0u, ad[j], lane);
            }
            rs0 += __shfl_xor_sync(~0u, rs0, 1); rs1 += __shfl_xor_sync(~0u, rs1, 1);
            rs0 += __shfl_xor_sync(~0u, rs0, 2); rs1 += __shfl_xor_sync(~0u, rs1, 2);
            rs0 = rsqrtf(fmaxf(rs0 * (1.f / kD) - mu0 * mu0, 0.f) + kEps);
            rs1 = rsqrtf(fmaxf(rs1 * (1.f / kD) - mu1 * mu1, 0.f) + kEps);
          }
          wgmma_rs_n64_tb<1>(e, a[8], a[9], a[10], a[11], dadd(db, 2 * 2048));
          wgmma_rs_n64_tb<1>(e, a[12], a[13], a[14], a[15], dadd(db, 3 * 2048));
          wg_commit();
          wg_wait<1>();
        } else {
          wg_wait<0>();
          keep(a);
          TM(4, tid == 0);
        }
        keep(d);
        const int atom = p == 0 ? 0 : 3 - p;
        const float f = 3 * cb + atom < 7 ? kQScale : 1.f;
        const float k0 = rs0 * f, k1 = rs1 * f;
#pragma unroll
        for (int jj = 0; jj < 8; jj++) {
          if (p < 2) wgmma_rs_n64_tb<1>(e, a[16 + 4 * jj], a[17 + 4 * jj], a[18 + 4 * jj], a[19 + 4 * jj], dadd(db, (4 + jj) * 2048));
          const int j = 8 * atom + jj;
          uint32_t dst = ad[j % 7] + (j / 7) * 16384;
          if (j >= 21 && dst >= sb + A_STG + 7 * 8192) dst -= 7 * 8192;
          sts32(dst, pack2(d[4 * jj] * k0, d[4 * jj + 1] * k0));
          sts32(dst + 512, pack2(d[4 * jj + 2] * k1, d[4 * jj + 3] * k1));
          if (p == 0 && jj >= 4) {
            const uint32_t u = ((kPolyU >> warp) & 1) ? 0x3F80u : 0u;
            const int pr = warp * 16 + (lane & 15), ls = 2 * (jj - 4) + hi, s = 7 * cb - 1 + ls;
            const uint32_t x0 = s < 16 ? 0u : (s < 32 ? (0x3F80u | (u << 16)) : 0x3F80u);
            const uint32_t x1 = (s >= 16 && s < 32) ? (u | (u << 16)) : 0u;
            if (ls < 7) sts64(sb + A_STG + ls * 8192 + pr * 64 + ((3 ^ ((pr >> 1) & 3)) << 4) + 8, x0, x1);
          }
        }
        if (p == 2) TM(5, tid == 0);
        if (p < 2) {
#pragma unroll
          for (int t = 12; t < 15; t++) wgmma_rs_n64_tb<1>(e, a[4 * t], a[4 * t + 1], a[4 * t + 2], a[4 * t + 3], dadd(db, t * 2048));
        }
        fence_async();
        __syncwarp();
        if (lane == 0) mbar_arrive(bar + 8 * (PST + p * 4 + (warp >> 1)));
        if (p < 2) {
#pragma unroll
          for (int t = 15; t < 28; t++) wgmma_rs_n64_tb<1>(e, a[4 * t], a[4 * t + 1], a[4 * t + 2], a[4 * t + 3], dadd(db, t * 2048));
          wg_commit();
        }
      }
      TM(37, tid == 0);
      if (cb <= 4) {
#pragma unroll
        for (int ls = 0; ls < 8; ls++) {
          const int elo = ls == 0 ? 7 - cb : 0, ehi = ls == 7 ? 6 - cb : 7;
          const uint32_t rb = sb + A_STG + (ls % 7) * 8192 + (warp * 16 + lr) * 64, sw = (lr >> 1) & 3;
          uint32_t k[8];
          ldsm4(rb + ((hi ^ sw) << 4), k[0], k[1], k[2], k[3]);
          ldsm4(rb + (((2 + hi) ^ sw) << 4), k[4], k[5], k[6], k[7]);
#pragma unroll
          for (int i = 0; i < 8; i++) { const int e = (i >> 1) * 2 + (c >> 1); if (e < elo || e >= ehi) k[i] = 0; }
          float q0[4] = {0, 0, 0, 0}, q1[4] = {0, 0, 0, 0};
          hmma(q0, k[0], k[1], k[2], k[3], k[0], k[2]); hmma(q1, k[0], k[1], k[2], k[3], k[1], k[3]);
          hmma(q0, k[4], k[5], k[6], k[7], k[4], k[6]); hmma(q1, k[4], k[5], k[6], k[7], k[5], k[7]);
          const float m = c == (g >> 1) ? fmaxf((g & 1) ? q0[1] : q0[0], (g & 1) ? q1[3] : q1[2]) : 0.f;
          const unsigned mx = __reduce_max_sync(~0u, __float_as_uint(m));
          if (lane == 0) sts32(sb + AUX_NR + warp * 32 + ls * 4, mx);
        }
        fence_async();
        __syncwarp();
        if (el) {
          bulk_st(scr->nrm + (cb * 128 + ra * 8 + warp) * 8, sb + AUX_NR + warp * 32, 32);
          bulk_commit(); bulk_wait();
        }
      }
      if (el) mbar_arrive(bar + 8 * ASTG);
      __syncwarp();
      TM(7, tid == 0); TM(63, tid == 128);
    }
    reg_dec<128>();
  }

  {
    LANE_VARS
    uint32_t q[8];
    const uint32_t qb = sb + B_Q + (warp * 16 + lr) * 64, qsw = (lr >> 1) & 3;
    mbar_wait(bar + 8 * QF, 0);
    TM(9, tid == 0);
    ldsm4(qb + ((hi ^ qsw) << 4), q[0], q[1], q[2], q[3]);
    ldsm4(qb + (((2 + hi) ^ qsw) << 4), q[4], q[5], q[6], q[7]);
    const bool fast = __all_sync(~0u, ((lds32(sb + AUX_EP + 4) >> (4 * wg)) & 15u) == 15u);
    float o[16], s[32];
    uint32_t p[16];
#pragma unroll
    for (int i = 0; i < 16; i++) { o[i] = 0.f; p[i] = 0; }
#pragma unroll
    for (int i = 0; i < 32; i++) s[i] = 0.f;
    const uint64_t dk0 = mkdesc(sb + B_KV, 16, 512, 2), dv0 = mkdesc(sb + B_KV + 8192, 512, 512, 2);
    const unsigned char* const kg = scr->qkv + blob_off(16 + head, 0);
    const uint32_t duty = (warp & 3) == 0 ? (0x1111u << wg) & 0x1FF8u : (warp == 9 ? 2u : 0u);
    auto do_duty = [&](int t, int st) {
      if (t == 1) {
        if (elect_one()) {
          if (cw < 7) {
            mbar_expect(bar + 8 * WOF, 65536); tma_3d(sb, &P.wo, bar + 8 * WOF, cw * 64, 0, 0);
            mbar_expect(bar + 8 * XRF, U); tma_2d(sb + C_XR, &P.x, bar + 8 * XRF, cw * 64, rw * 128);
          }
          mbar_expect(bar + 8 * W1F, U);
          tma_3d(sb + w1_off(0), &P.w1, bar + 8 * W1F, 0, 0, (cs * 7) >> 1);
          l2_prefetch((const char*)P.w1p + b * 12544, 12544);
          l2_prefetch((const char*)P.w2p + b * 12544, 12544);
        }
      } else {
        const int s2 = st >= 3 ? st - 3 : st + NS - 3, nt = t - 3 + NS;
        mbar_wait(bar + 8 * (KVE + s2), t - 3 >= NS);
        if (elect_one()) {
          mbar_expect(bar + 8 * (KVF + s2), 16384);
          bulk_ld(sb + B_KV + s2 * 16384, kg + nt * 16384, 16384, bar + 8 * (KVF + s2));
        }
      }
      __syncwarp();
    };
    const bool lane0 = lane == 0;
    TM(10, tid == 0);
    int st = 0, ph = 0;
    if (fast) {
      if (c == 2) q[6] = q[7] = pack2(-40.f, 352.f);
      if (c == 3) q[6] = q[7] = pack2(3.f, 0.00541f);
      const PolyC k = {lds32(sb + AUX_EP + 8), lds32(sb + AUX_EP + 12), 0xA65DA65Du, 0x0DF50DF5u};
      keep(q); keep(o); keep(s); keep(p);
      uint32_t prev = bar + 8 * DUMMY;
      mbar_wait(bar + 8 * KVF, 0);
#pragma unroll 1
      for (int t = 0; t < 16; t++) {
        const int sn = st == NS - 1 ? 0 : st + 1;
#pragma unroll
        for (int hf = 0; hf < 2; hf++) {
          const uint64_t dk = dadd(dk0, st * 16384 + hf * 4096), dv = dadd(dv0, st * 16384 + hf * 4096);
          wg_fence();
          wgmma_rs_n64<0>(s, q[0], q[1], q[2], q[3], dk);
          wgmma_rs_n64<1>(s, q[4], q[5], q[6], q[7], dadd(dk, 32));
          wg_commit();
          if (hf == 1) { if (sn == 0) ph ^= 1; if (t < 15) mbar_wait(bar + 8 * (KVF + sn), ph); }
          else if ((duty >> t) & 1) do_duty(t, st);
          wg_wait<0>();
          keep(s); keep(p);
          if (hf == 0 && lane0) mbar_arrive(prev);
#pragma unroll
          for (int j = 0; j < 16; j++)
            p[j] = ((kPolyU >> (4 * hf + (j >> 2))) & 1) ? exp2_pair(s[2 * j], s[2 * j + 1], k) : pack2(ex2(s[2 * j]), ex2(s[2 * j + 1]));
          keep(p);
          wg_fence();
#pragma unroll
          for (int u = 0; u < 4; u++) {
            if ((kPolyU >> (4 * hf + u)) & 1) wgmma_rs_n32_tb<1, -1>(o, p[4 * u], p[4 * u + 1], p[4 * u + 2], p[4 * u + 3], dadd(dv, u * 1024));
            else wgmma_rs_n32_tb<1, 1>(o, p[4 * u], p[4 * u + 1], p[4 * u + 2], p[4 * u + 3], dadd(dv, u * 1024));
          }
          wg_commit();
        }
        prev = bar + 8 * (KVE + st);
        st = sn;
      }
    } else {
      float m0 = -INFINITY, m1 = -INFINITY;
      keep(q); keep(o); keep(s); keep(p);
#pragma unroll 1
      for (int t2 = 0; t2 < 32; t2++) {
        const int hf = t2 & 1;
        if (hf == 0) mbar_wait(bar + 8 * (KVF + st), ph);
        const uint64_t dk = dadd(dk0, st * 16384 + hf * 4096), dv = dadd(dv0, st * 16384 + hf * 4096);
        wg_fence();
        wgmma_rs_n64<0>(s, q[0], q[1], q[2], q[3], dk);
        wgmma_rs_n64<1>(s, q[4], q[5], q[6], q[7], dadd(dk, 32));
        wg_commit();
        wg_wait<0>();
        keep(s); keep(p); keep(o);
        if (hf == 0) {
          if (t2 > 0 && lane0) mbar_arrive(bar + 8 * (KVE + (st == 0 ? NS : st) - 1));
          if ((duty >> (t2 >> 1)) & 1) do_duty(t2 >> 1, st);
        }
        float x0 = m0, x1 = m1;
#pragma unroll
        for (int j = 0; j < 8; j++) {
          x0 = fmaxf(x0, fmaxf(s[4 * j], s[4 * j + 1]));
          x1 = fmaxf(x1, fmaxf(s[4 * j + 2], s[4 * j + 3]));
        }
        x0 = fmaxf(x0, __shfl_xor_sync(~0u, x0, 1)); x1 = fmaxf(x1, __shfl_xor_sync(~0u, x1, 1));
        x0 = fmaxf(x0, __shfl_xor_sync(~0u, x0, 2)); x1 = fmaxf(x1, __shfl_xor_sync(~0u, x1, 2));
        const float f0 = ex2(m0 - x0), f1 = ex2(m1 - x1);
        m0 = x0; m1 = x1;
#pragma unroll
        for (int j = 0; j < 4; j++) { o[4 * j] *= f0; o[4 * j + 1] *= f0; o[4 * j + 2] *= f1; o[4 * j + 3] *= f1; }
#pragma unroll
        for (int j = 0; j < 8; j++) {
          p[2 * j] = pack2(ex2(s[4 * j] - m0), ex2(s[4 * j + 1] - m0));
          p[2 * j + 1] = pack2(ex2(s[4 * j + 2] - m1), ex2(s[4 * j + 3] - m1));
        }
        keep(p); keep(o);
        wg_fence();
#pragma unroll
        for (int u = 0; u < 4; u++) wgmma_rs_n32_tb<1, 1>(o, p[4 * u], p[4 * u + 1], p[4 * u + 2], p[4 * u + 3], dadd(dv, u * 1024));
        wg_commit();
        if (hf == 1 && ++st == NS) { st = 0; ph ^= 1; }
      }
    }
    wg_wait<0>();
    keep(o);
    if (lane0) mbar_arrive(bar + 8 * KVD);
    TM(11 + wg, (tid & 127) == 0);
    const float i0 = rcp_fast(__shfl_sync(~0u, o[12], (lane & ~3) + 2)), i1 = rcp_fast(__shfl_sync(~0u, o[14], (lane & ~3) + 2));
    stsm4(qb + ((hi ^ qsw) << 4), pack2(o[0] * i0, o[1] * i0), pack2(o[2] * i1, o[3] * i1),
          pack2(o[4] * i0, o[5] * i0), pack2(o[6] * i1, o[7] * i1));
    stsm4(qb + (((2 + hi) ^ qsw) << 4), pack2(o[8] * i0, o[9] * i0), pack2(o[10] * i1, o[11] * i1),
          pack2(o[12] * i0, o[13] * i0), pack2(o[14] * i1, o[15] * i1));
    fence_async();
    __syncwarp();
    if (elect_one()) {
      const int ort = 2 * qr + (warp >> 3);
      bulk_st(scr->o + (size_t)(ort * 16 + head) * 8192 + (warp & 7) * 1024, sb + B_Q + warp * 1024, 1024);
      bulk_commit(); bulk_wait();
      mbar_arrive(bar + 8 * (warp < 8 ? BDONE : BD1));
    }
    __syncwarp();
    if (warp == 9 || warp == 10) {
      mbar_wait(bar + 8 * (warp == 9 ? BDONE : BD1), 0);
      if (elect_one()) signal(&scr->cnt[(16 + 2 * qr + (warp - 9)) * 32]);
      TM(98 + warp - 9, lane == 0);
      __syncwarp();
    }
    TM(15, tid == 0);
  }

  const int odd = cs & 1, pr = cs >> 1;
  const uint32_t rmask = pr == 3 ? 0x34u : (odd ? 0x14u : 0x1Cu);
  auto chunk_of = [&](int st) {
    const uint32_t emask = pr == 3 ? (odd ? 0x4Bu : 0x74u) : (odd ? 0x2Bu : 0x5Cu);
    const uint32_t below = (1u << st) - 1;
    if ((emask >> st) & 1) return 2 * ((pr + 1 + __popc(emask & below)) & 3);
    const int n = __popc(~emask & below), v = pr == 3 ? n : pr + 1 + n;
    return 2 * (v >= 3 ? v - 3 : v) + 1;
  };
  auto src_of = [&](int k) {
    const int sv = pr - 1 - k;
    return !odd ? (sv & 3) : (pr == 0 ? (k == 1 ? 3 : 2 - (k >> 1)) : (k == 2 ? 3 : (sv < 0 ? sv + 3 : sv)));
  };
  if (wg >= 2) {
    reg_dec<64>();
    LANE_VARS
    const unsigned ep = __shfl_sync(~0u, lds32(sb + AUX_EP), 0);
    const int w = warp - 8;
    uint32_t res[16];
    auto grab_residual = [&]() {
      if (cs < 7) {
        mbar_wait(bar + 8 * (HF + cs), 0);
#pragma unroll
        for (int t = 0; t < 4; t++)
          ldsm4(sb + C_O + cs * U + (w * 16 + lr) * 128 + (((2 * t + hi) ^ (lr & 7)) << 4), res[4 * t], res[4 * t + 1], res[4 * t + 2], res[4 * t + 3]);
        if (lane == 0) { sts32(sb + AUX_EP + 20, res[15]); mbar_arrive(bar + 8 * (RESD + w)); }
      }
    };
    if (warp != 8) grab_residual();
    if (warp == 8) {
      const bool el = elect_one();
      auto ld_w1 = [&](int kb, int half) {
        if (el) { mbar_expect(bar + 8 * (W1F + kb), U); tma_3d(sb + w1_off(kb) + half * U, &P.w1, bar + 8 * (W1F + kb), 0, kb * 64, ((cs * 7) >> 1) + 2 * half); }
      };
      auto ld_w2 = [&](int st) {
        if (el) { mbar_expect(bar + 8 * (W2F + st), 28672); tma_2d(sb + w2_off(st), &P.w2, bar + 8 * (W2F + st), chunk_of(st) * 64, cs * 224); }
      };
      if (cw < 7) {
        const unsigned char* const og = scr->o + (size_t)rw * 16 * 8192;
        mbar_wait(bar + 8 * KVD, 0);
        poll(&scr->cnt[(16 + rw) * 32], 16 * ep);
        if (el) {
#pragma unroll
          for (int i = 1; i < 8; i++) bulk_ld(sb + C_O + i * 16384, og + i * 16384, 16384, bar + 8 * (OF + i));
        }
        mbar_wait(bar + 8 * BDONE, 0); mbar_wait(bar + 8 * BD1, 0);
        if (el) bulk_ld(sb + C_O, og, 16384, bar + 8 * OF);
        mbar_wait(bar + 8 * XRD, 0);
        ld_w1(0, 1);
        TM(16, lane == 0);
        mbar_wait(bar + 8 * HST, 0);
        if (el) signal(&scr->cnt[(32 + rw) * 32]);
      } else {
        ld_w1(0, 1);
        mbar_wait(bar + 8 * BDONE, 0); mbar_wait(bar + 8 * BD1, 0);
      }
      ld_w1(1, 0); ld_w1(1, 1);
      poll(&scr->cnt[(32 + (ALIGN == 0 ? rt : (ALIGN == 1 ? (rt & ~3) + (lane & 3) : (lane & 15)))) * 32], 7 * ep);
      TM(22, lane == 0);
      if (el) {
        mbar_expect(bar + 8 * STF, 7168);
        bulk_ld(sb + C_STG, scr->st + rt * 8 * 128, 7168, bar + 8 * STF);
#pragma unroll
        for (int kb = 0; kb < 7; kb++) {
          mbar_expect(bar + 8 * (HF + kb), U); tma_2d(sb + C_O + kb * U, &P.h, bar + 8 * (HF + kb), kb * 64, rt * 128);
          if (kb == 2) { ld_w1(2, 0); ld_w1(2, 1); }
        }
      }
      grab_residual();
      auto freed = [&](int i) { mbar_wait(bar + 8 * i, 0); };
      freed(HREL + 0); freed(HREL + 1); ld_w1(3, 0); ld_w1(3, 1);
      freed(W1REL + 0); ld_w1(4, 0); ld_w1(4, 1);
      freed(W1REL + 1); ld_w1(5, 0); ld_w1(5, 1);
      freed(HREL + 2); freed(HREL + 3); ld_w1(6, 0); ld_w1(6, 1);
      freed(HREL + 4); freed(HREL + 5); ld_w2(0);
      freed(HREL + 6); ld_w2(1);
      freed(W1REL + 3); ld_w2(2);
      freed(W1REL + 4); ld_w2(3);
      freed(W1REL + 6); ld_w2(4);
      freed(W2REL + 0); ld_w2(5);
      freed(W2REL + 1); ld_w2(6);
      __syncwarp();
    }
    if (cs < 7) {
      const uint32_t tag = (ep & 1u) | ((ep & 2u) << 15);
      const uint4* const pbase = scr->part + (size_t)(rt * 8 + cs) * 4 * 1024 + w * 128 + lane;
      const uint32_t eye = g == 2 * c ? 0x3F80u : (g == 2 * c + 1 ? 0x3F800000u : 0u);
      float sum[8][4];
#pragma unroll
      for (int j = 0; j < 16; j++) { sum[j >> 1][(j & 1) * 2] = bf_lo(res[j]); sum[j >> 1][(j & 1) * 2 + 1] = bf_hi(res[j]); }
#pragma unroll 1
      for (int k = 0; k < 2; k++) {
        const int src = src_of(k);
        if (k == 0) mbar_wait(bar + 8 * (W2REL + PACE0), 0);
        const uint4* pp = pbase + src * 1024;
        uint32_t v[16];
        TM(40 + 3 * k, tid == 288);
        for (int it = 0; it < 200000; it++) {
          uint32_t t = tag;
          if (lane == 31) t = ld_relaxed(reinterpret_cast<const uint32_t*>(pp + 96) + 3);
          if (!__any_sync(~0u, ((t ^ tag) & 0x00010001u) != 0)) break;
        }
        for (int it = 0; it < 200000; it++) {
#pragma unroll
          for (int qd = 0; qd < 4; qd++) ld_pkt(pp + qd * 32, &v[4 * qd]);
          const uint32_t bad = ((v[3] ^ tag) | (v[7] ^ tag) | (v[11] ^ tag) | (v[15] ^ tag)) & 0x00010001u;
          if (!__any_sync(~0u, bad != 0)) break;
        }
        TM(41 + 3 * k, tid == 288);
#pragma unroll
        for (int t = 0; t < 4; t++) {
          hmma(sum[2 * t], v[4 * t], v[4 * t + 1], v[4 * t + 2], v[4 * t + 3], eye, 0u);
          hmma(sum[2 * t + 1], v[4 * t], v[4 * t + 1], v[4 * t + 2], v[4 * t + 3], 0u, eye);
        }
        TM(42 + 3 * k, tid == 288 && sum[7][3] != 1.2345f);
      }
      TM(33 + (wg & 1), (tid & 127) == 0);
      mbar_wait(bar + 8 * (W2REL + 2), 0); mbar_wait(bar + 8 * (W2REL + 3), 0);
#pragma unroll
      for (int i = 0; i < 8; i++) sts128(sb + C_HAND + i * 4096 + (tid & 255) * 16, sum[i][0], sum[i][1], sum[i][2], sum[i][3]);
      __syncwarp();
      if (lane == 0) mbar_arrive(bar + 8 * (HAND + w));
    }
  } else {
    reg_inc<192>();
    LANE_VARS
    const uint32_t rb = sb + C_O + (warp * 16 + lr) * 128, sw = lr & 7;
    if (cw < 7) {
      uint32_t xr[16];
      mbar_wait(bar + 8 * XRF, 0);
#pragma unroll
      for (int t = 0; t < 4; t++) ldsm4(rb - C_O + C_XR + (((2 * t + hi) ^ sw) << 4), xr[4 * t], xr[4 * t + 1], xr[4 * t + 2], xr[4 * t + 3]);
      if (lane == 0) { sts32(sb + AUX_EP + 20, xr[15]); mbar_arrive(bar + 8 * XRD); }
      float acc[32];
      const uint64_t da0 = mkdesc(sb + C_O + wg * 4096, 16, 512, 2), db0 = mkdesc(sb, 1024, 1024, 1);
      mbar_wait(bar + 8 * WOF, 0);
#pragma unroll
      for (int n = 0; n < 8; n++) {
        const int i = (n + 1) & 7;
        mbar_wait(bar + 8 * (OF + i), 0);
        if (n == 0) TM(17, tid == 0);
        if (n == 7) TM(18, tid == 0);
        wg_fence();
#pragma unroll
        for (int t = 0; t < 4; t++) {
          const uint64_t da = dadd(da0, i * 16384 + (t >> 1) * 8192 + (t & 1) * 32), db = dadd(db0, (i * 4 + t) * 2048);
          if (n == 0 && t == 0) wgmma_ss_n64_tb<0>(acc, da, db); else wgmma_ss_n64_tb<1>(acc, da, db);
        }
        wg_commit();
      }
      wg_wait<0>();
      keep(acc);
      if (lane == 0) mbar_arrive(bar + 8 * CMMA);
      TM(19, tid == 0);
      float s0 = 0, s1 = 0, q0 = 0, q1 = 0;
#pragma unroll
      for (int j = 0; j < 16; j++) {
        xr[j] = pack2(acc[2 * j] + bf_lo(xr[j]), acc[2 * j + 1] + bf_hi(xr[j]));
        const float a0 = bf_lo(xr[j]), a1 = bf_hi(xr[j]);
        if (j & 1) { s1 += a0 + a1; q1 += a0 * a0 + a1 * a1; } else { s0 += a0 + a1; q0 += a0 * a0 + a1 * a1; }
      }
      mbar_wait(bar + 8 * CMMA, 0);
#pragma unroll
      for (int t = 0; t < 4; t++) stsm4(rb + 7 * U + (((2 * t + hi) ^ sw) << 4), xr[4 * t], xr[4 * t + 1], xr[4 * t + 2], xr[4 * t + 3]);
#pragma unroll
      for (int sh = 1; sh < 4; sh <<= 1) {
        s0 += __shfl_xor_sync(~0u, s0, sh); q0 += __shfl_xor_sync(~0u, q0, sh);
        s1 += __shfl_xor_sync(~0u, s1, sh); q1 += __shfl_xor_sync(~0u, q1, sh);
      }
      if (c < 2) sts64(sb + AUX_KM + (warp * 16 + g + 8 * c) * 8, __float_as_uint(c ? s1 : s0), __float_as_uint(c ? q1 : q0));
      fence_async();
      __syncwarp();
      if (elect_one()) {
        tma_2d_store(&P.hst, sb + C_STG + warp * 2048, cw * 64, rw * 128 + warp * 16);
        bulk_st(scr->st + (rw * 8 + cw) * 128 + warp * 16, sb + AUX_KM + warp * 128, 128);
        bulk_commit(); bulk_wait();
        TM(20, warp == 0);
        mbar_arrive(bar + 8 * HST);
      }
      __syncwarp();
      TM(21, tid == 0);
    }
    uint32_t rs0, rs1, m0, m1;
    mbar_wait(bar + 8 * STF, 0);
    TM(39, tid == 0);
    {
      const uint32_t sa = sb + C_STG + (2 * c * 128 + warp * 16 + g) * 8;
      const uint2 z = make_uint2(0, 0);
      const uint2 u0 = lds64(sa), v0 = lds64(sa + 64), u1 = c < 3 ? lds64(sa + 1024) : z, v1 = c < 3 ? lds64(sa + 1088) : z;
      float s0 = __uint_as_float(u0.x) + __uint_as_float(u1.x), q0 = __uint_as_float(u0.y) + __uint_as_float(u1.y);
      float s1 = __uint_as_float(v0.x) + __uint_as_float(v1.x), q1 = __uint_as_float(v0.y) + __uint_as_float(v1.y);
#pragma unroll
      for (int sh = 1; sh < 4; sh <<= 1) {
        s0 += __shfl_xor_sync(~0u, s0, sh); q0 += __shfl_xor_sync(~0u, q0, sh);
        s1 += __shfl_xor_sync(~0u, s1, sh); q1 += __shfl_xor_sync(~0u, q1, sh);
      }
      const float mu0 = s0 * (1.f / kD), mu1 = s1 * (1.f / kD);
      const float r0 = 0.5f * rsqrtf(fmaxf(q0 * (1.f / kD) - mu0 * mu0, 0.f) + kEps);
      const float r1 = 0.5f * rsqrtf(fmaxf(q1 * (1.f / kD) - mu1 * mu1, 0.f) + kEps);
      rs0 = pack2(r0, r0); rs1 = pack2(r1, r1);
      const float o0 = -mu0 * bf_lo(rs0), o1 = -mu1 * bf_lo(rs1);
      m0 = pack2(o0, o0); m1 = pack2(o1, o1);
    }
    auto silu2 = [&](float t0, float t1) { return pack2(fmaf(t0, tanh_fast(t0), t0), fmaf(t1, tanh_fast(t1), t1)); };
    uint32_t a[2][16];
    auto load_a = [&](int kb, uint32_t (&ab)[16]) {
#pragma unroll
      for (int t = 0; t < 4; t++) ldsm4(rb + kb * U + (((2 * t + hi) ^ sw) << 4), ab[4 * t], ab[4 * t + 1], ab[4 * t + 2], ab[4 * t + 3]);
    };
    auto norm_a = [&](uint32_t (&ab)[16]) {
#pragma unroll
      for (int i = 0; i < 16; i++) ab[i] = hfma2(ab[i], (i & 1) ? rs1 : rs0, (i & 1) ? m1 : m0);
    };
    const uint64_t dw1 = mkdesc(sb, 8192, 1024, 1), dwA = dadd(dw1, odd * 8192), dwC = dadd(dw1, odd ? 64 : 3 * 8192);
    mbar_wait(bar + 8 * HF, 0);
    TM(24, tid == 0);
    load_a(0, a[0]);
    norm_a(a[0]);
    float cA[96], cC[16];
#pragma unroll
    for (int kb = 0; kb < 7; kb++) {
      uint32_t(&ab)[16] = a[kb & 1];
      uint32_t(&an)[16] = a[(kb + 1) & 1];
      const uint64_t d1 = dadd(dwA, w1_off(kb)), d2 = dadd(dwC, w1_off(kb));
      mbar_wait(bar + 8 * (W1F + kb), 0);
      if (kb == 0) TM(23, tid == 0);
      keep(ab);
      wg_fence();
#pragma unroll
      for (int t = 0; t < 4; t++) {
        if (kb == 0 && t == 0) {
          wgmma_rs_n192_tb<0>(cA, ab[0], ab[1], ab[2], ab[3], d1);
          wgmma_rs_n32_tb<0>(cC, ab[0], ab[1], ab[2], ab[3], d2);
        } else {
          wgmma_rs_n192_tb<1>(cA, ab[4 * t], ab[4 * t + 1], ab[4 * t + 2], ab[4 * t + 3], dadd(d1, t * 2048));
          wgmma_rs_n32_tb<1>(cC, ab[4 * t], ab[4 * t + 1], ab[4 * t + 2], ab[4 * t + 3], dadd(d2, t * 2048));
        }
        if (t == 0) {
          wg_commit();
          if (cs == kb) mbar_wait(bar + 8 * (RESD + warp), 0);
          if (kb < 6) mbar_wait(bar + 8 * (HF + kb + 1), 0);
          if (kb > 0) { wg_wait<1>(); keep(an); }
          if (kb < 6) load_a(kb + 1, an);
          if (lane == 0) {
            mbar_arrive(bar + 8 * (HREL + kb));
            if (kb > 0) mbar_arrive(bar + 8 * (W1REL + kb - 1));
            if (kb == 6) mbar_arrive_peer(peer_addr(bar + 8 * CRED, odd ^ 1));
          }
        }
        if (t == 2 && kb < 6) { norm_a(an); keep(an); }
      }
      wg_commit();
    }
    uint32_t act[56];
    TM(26, tid == 0);
    {
      float acc[2][32];
      const uint32_t tag = lds32(sb + AUX_EP + 16);
      uint4* const pbase = scr->part + (size_t)rt * 8 * 4 * 1024 + pr * 1024 + warp * 128;
      const uint32_t pin = peer_addr(sb + C_IN + warp * 2048 + lane * 16, odd ^ 1), pbar = peer_addr(bar + 8 * (INB + wg), odd ^ 1);
      const bool el = elect_one();
      int nin = 0, nout = 0;
      uint64_t dA = dadd(dw1, odd ? 32 * 128 : 0), dC = dadd(dw1, odd ? 0 : 192 * 128);
      auto mma2 = [&](int st, int t, float (&d)[32]) {
        const uint64_t db = t < 12 ? dadd(dA, w2_off(st) + t * 2048) : dadd(dC, w2_off(st) + (t - 12) * 2048);
        if (t == 0) wgmma_rs_n64_tb<0>(d, act[0], act[1], act[2], act[3], db);
        else wgmma_rs_n64_tb<1>(d, act[4 * t], act[4 * t + 1], act[4 * t + 2], act[4 * t + 3], db);
      };
      auto send_q = [&](const float (&d)[32], int qd) {
        st_async(pin + nout * U + qd * 512, pack2(d[8 * qd], d[8 * qd + 1]), pack2(d[8 * qd + 2], d[8 * qd + 3]),
                 pack2(d[8 * qd + 4], d[8 * qd + 5]), pack2(d[8 * qd + 6], d[8 * qd + 7]), pbar + 16 * nout);
      };
      auto reduce_q = [&](const float (&d)[32], const uint32_t (&v)[16], int qd, uint32_t inb) {
        sts128u(inb + qd * 512 + lane * 16, hadd2(v[4 * qd], pack2(d[8 * qd], d[8 * qd + 1])),
                hadd2(v[4 * qd + 1], pack2(d[8 * qd + 2], d[8 * qd + 3])), hadd2(v[4 * qd + 2], pack2(d[8 * qd + 4], d[8 * qd + 5])),
                (hadd2(v[4 * qd + 3], pack2(d[8 * qd + 6], d[8 * qd + 7])) & 0xFFFEFFFEu) | tag);
      };
      mbar_wait(bar + 8 * W2F, 0);
      wg_wait<0>();
      TM(25, tid == 0);
      keep(cA); keep(cC); keep(a[0]);
      if (lane == 0) mbar_arrive(bar + 8 * (W1REL + 6));
      auto pre = [&](int i) -> float { return i < 96 ? cA[i < 96 ? i : 0] : cC[i < 96 ? 0 : i - 96]; };
      float th[2][8];
#pragma unroll
      for (int i = 0; i < 8; i++) th[0][i] = tanh_fast(pre(i));
#pragma unroll
      for (int t = 0; t < 14; t++) {
        if (SFEN) asm volatile("pmevent 0;");
        if (t < 13) {
#pragma unroll
          for (int i = 0; i < 8; i++) th[(t + 1) & 1][i] = tanh_fast(pre(8 * t + 8 + i));
        }
        if (SFEN > 1) asm volatile("pmevent 0;");
#pragma unroll
        for (int j = 0; j < 4; j++) {
          const float t0 = pre(8 * t + 2 * j), t1 = pre(8 * t + 2 * j + 1);
          act[4 * t + j] = pack2(fmaf(t0, th[t & 1][2 * j], t0), fmaf(t1, th[t & 1][2 * j + 1], t1));
          asm volatile("" : "+r"(act[4 * t + j])::"memory");
        }
        if (t == C1D) { mbar_wait(bar + 8 * (W2F + 1), 0); mbar_wait(bar + 8 * CRED, 0); }
        wg_fence();
        mma2(0, t, acc[0]);
        if (t >= C1D && t < C1D + 8) mma2(1, t - C1D, acc[1]);
      }
      wg_commit();
      TM(27 + wg, (tid & 127) == 0);
#pragma unroll
      for (int st = 0; st < 7; st++) {
        float(&d)[32] = acc[st & 1];
        float(&e)[32] = acc[(st + 1) & 1];
        const bool own = st == 6 && cs < 7, red = st == 2 || st == 4 || ((st == 3 || st == 5) && ((rmask >> st) & 1));
        uint32_t v[16];
        if (st == 4) {
          const uint32_t z = __shfl_sync(~0u, (uint32_t)dA, 0) - (uint32_t)dA;
          dA = dadd(dA, z); dC = dadd(dC, z);
        }
        constexpr int T0 = 0;
        const int t0 = st == 0 ? 8 : T0;
        if (st < 6) {
          if (st >= 1) mbar_wait(bar + 8 * (W2F + st + 1), 0);
          wg_fence();
          mma2(st + 1, t0, e); mma2(st + 1, t0 + 1, e);
          wg_commit();
          wg_wait<1>();
        } else {
          wg_wait<0>();
        }
        keep(d);
        TM(88 + st, tid == 0);
        if (lane == 0) mbar_arrive(bar + 8 * (W2REL + st));
        const uint32_t inb = sb + C_IN + nin * U + warp * 2048;
        if (red || own) {
          mbar_wait(bar + 8 * (INB + 2 * nin + wg), 0);
#pragma unroll
          for (int qd = 0; qd < 4; qd++) lds128u(inb + qd * 512 + lane * 16, &v[4 * qd]);
          nin++;
        }
        if (st == 3 || st >= 5) {
          if (st < 6) { mma2(st + 1, 2, e); mma2(st + 1, 3, e); mma2(st + 1, 4, e); }
          if (red) {
#pragma unroll
            for (int qd = 0; qd < 4; qd++) reduce_q(d, v, qd, inb);
          } else if (!own) {
#pragma unroll
            for (int qd = 0; qd < 4; qd++) send_q(d, qd);
          }
        } else {
#pragma unroll
          for (int qd = 0; qd < 4; qd++) {
            if (qd < 3) mma2(st + 1, t0 + 2 + qd, e);
            if (red) reduce_q(d, v, qd, inb); else send_q(d, qd);
          }
        }
        if (st < 6) mma2(st + 1, t0 + 5, e);
        if (!red && !own) nout++;
        if (FWD == 0 && red) { fence_async(); __syncwarp(); if (el) bulk_st(pbase + chunk_of(st) * 4 * 1024, inb, 2048); }
        if (st >= 1 && st < 6) {
#pragma unroll
          for (int t = 6; t < 14; t++) mma2(st + 1, t, e);
        }
        if (FWD == 1 && red) { fence_async(); __syncwarp(); if (el) bulk_st(pbase + chunk_of(st) * 4 * 1024, inb, 2048); }
        if (st < 6) wg_commit();
        if (own) {
          TM(29 + wg, (tid & 127) == 0);
          const uint4* pp = scr->part + (size_t)((rt * 8 + cs) * 4 + src_of(2)) * 1024 + warp * 128 + lane;
          uint32_t x[16];
          for (int it = 0; it < 200000; it++) {
#pragma unroll
            for (int qd = 0; qd < 4; qd++) ld_pkt(pp + qd * 32, &x[4 * qd]);
            if (it == 0) {
#pragma unroll
              for (int i = 0; i < 16; i++) { d[2 * i] += bf_lo(v[i]); d[2 * i + 1] += bf_hi(v[i]); }
              mbar_wait(bar + 8 * (HAND + warp), 0);
#pragma unroll
              for (int i = 0; i < 8; i++) {
                const float4 u = lds128(sb + C_HAND + i * 4096 + tid * 16);
                d[4 * i] += u.x; d[4 * i + 1] += u.y; d[4 * i + 2] += u.z; d[4 * i + 3] += u.w;
              }
            }
            const uint32_t bad = ((x[3] ^ tag) | (x[7] ^ tag) | (x[11] ^ tag) | (x[15] ^ tag)) & 0x00010001u;
            if (!__any_sync(~0u, bad != 0)) break;
          }
#pragma unroll
          for (int t = 0; t < 4; t++)
            stsm4(rb - C_O + C_OUT + (((2 * t + hi) ^ sw) << 4),
                  pack2(d[8 * t] + bf_lo(x[4 * t]), d[8 * t + 1] + bf_hi(x[4 * t])), pack2(d[8 * t + 2] + bf_lo(x[4 * t + 1]), d[8 * t + 3] + bf_hi(x[4 * t + 1])),
                  pack2(d[8 * t + 4] + bf_lo(x[4 * t + 2]), d[8 * t + 5] + bf_hi(x[4 * t + 2])), pack2(d[8 * t + 6] + bf_lo(x[4 * t + 3]), d[8 * t + 7] + bf_hi(x[4 * t + 3])));
          fence_async();
          __syncwarp();
          if (el) tma_2d_store(&P.out, sb + C_OUT + warp * 2048, cs * 64, rt * 128 + warp * 16);
        }
      }
      if (el) asm volatile("cp.async.bulk.commit_group;\ncp.async.bulk.wait_group.read 0;" ::: "memory");
      TM(31 + wg, (tid & 127) == 0);
    }
  }
  asm volatile("barrier.cluster.arrive.relaxed.aligned;\nbarrier.cluster.wait.aligned;" ::: "memory");
  {
  }
}

typedef CUresult (*EncodeFn)(CUtensorMap*, CUtensorMapDataType, cuuint32_t, void*, const cuuint64_t*, const cuuint64_t*,
                             const cuuint32_t*, const cuuint32_t*, CUtensorMapInterleave, CUtensorMapSwizzle,
                             CUtensorMapL2promotion, CUtensorMapFloatOOBfill);

void make_map(EncodeFn enc, CUtensorMap* m, const void* p, int rank, const int* dims, const int* strides, const int* box) {
  cuuint64_t gd[3], gs[2];
  cuuint32_t bx[3], es[3] = {1, 1, 1};
  for (int i = 0; i < rank; i++) { gd[i] = dims[i]; bx[i] = box[i]; }
  for (int i = 0; i + 1 < rank; i++) gs[i] = strides[i];
  enc(m, CU_TENSOR_MAP_DATA_TYPE_BFLOAT16, rank, const_cast<void*>(p), gd, gs, bx, es, CU_TENSOR_MAP_INTERLEAVE_NONE,
      CU_TENSOR_MAP_SWIZZLE_128B, CU_TENSOR_MAP_L2_PROMOTION_L2_128B, CU_TENSOR_MAP_FLOAT_OOB_FILL_NONE);
}
void make_2d(EncodeFn enc, CUtensorMap* m, const void* p, int rows, int cols, int box_rows) {
  const int d[2] = {cols, rows}, s[1] = {cols * 2}, b[2] = {64, box_rows};
  make_map(enc, m, p, 2, d, s, b);
}

}

extern "C" void kernel_launch(void* const* d_in, const int* in_sizes, int n_in, void* d_out, int out_size) {
  Params P;
  P.xp = (const __nv_bfloat16*)d_in[0];
  const void* wqkv = d_in[1];
  P.wqp = (const __nv_bfloat16*)wqkv;
  P.wop = (const __nv_bfloat16*)d_in[2];
  P.w1p = (const __nv_bfloat16*)d_in[4];
  P.w2p = (const __nv_bfloat16*)d_in[5];

  void* fn = nullptr;
  cudaDriverEntryPointQueryResult qr;
  cudaGetDriverEntryPoint("cuTensorMapEncodeTiled", &fn, cudaEnableDefault, &qr);
  EncodeFn enc = (EncodeFn)fn;
  void* sp = nullptr;
  cudaGetSymbolAddress(&sp, g_scr);
  P.scr = (Scratch*)sp;
  cudaFuncSetAttribute(k_block, cudaFuncAttributeMaxDynamicSharedMemorySize, SMEM);

  make_2d(enc, &P.x, P.xp, kS, kD, 128);
  make_2d(enc, &P.h, P.scr->h, kS, kD, 128);
  make_2d(enc, &P.hst, P.scr->h, kS, kD, 16);
  make_2d(enc, &P.out, d_out, kS, kD, 16);
  make_2d(enc, &P.w2, P.w2p, kF, kD, 224);
  make_2d(enc, &P.wa, wqkv, kD, 3 * kD, 64);
  make_2d(enc, &P.wb, wqkv, kD, 3 * kD, 224);
  { const int d[3] = {64, kD, 28}, s[2] = {kF * 2, 128}, b[3] = {64, 64, 2}; make_map(enc, &P.w1, P.w1p, 3, d, s, b); }
  { const int d[3] = {kD, 28, 16}, s[2] = {kD * 2, 28 * kD * 2}, b[3] = {64, 32, 16}; make_map(enc, &P.wo, P.wop, 3, d, s, b); }

  k_block<<<128, 512, SMEM, cudaStreamPerThread>>>(P);
}
```
